```python
import torch

def _softmax(x, axis=-1):
    return torch.softmax(x, dim=axis)
def _gelu(x):
    return torch.nn.functional.gelu(x, approximate="tanh")
def _silu(x):
    return torch.nn.functional.silu(x)
def _sigmoid(x):
    return torch.sigmoid(x)
def _layernorm(x, axis=-1, eps=1e-5):
    m = x.mean(dim=axis, keepdim=True)
    v = x.var(dim=axis, keepdim=True, unbiased=False)
    return (x - m) / torch.sqrt(v + eps)
def _scatter_add(tgt, idx, src, axis=0):
    return tgt.clone().index_add_(axis, idx, src)
def _segment_sum(src, seg, n):
    out = torch.zeros((n,) + src.shape[1:], dtype=src.dtype)
    return out.index_add_(0, seg, src)
def _pad(x, pw):
    flat = tuple(v for pair in reversed(pw) for v in pair)
    return torch.nn.functional.pad(x, flat)

kernel_name = 'standalone__batchnorm__sampling'

def setup_inputs():

    _w = (lambda a: (lambda t: t.to(torch.bfloat16) if t.is_floating_point() else t)(torch.as_tensor(a)))
    B, S, C = 1024, 32, 448
    K = 3
    return {
        "x": _w((lambda *s: torch.randn(*s, dtype=torch.bfloat16) * 0.05)(B, S, C)),
        "w": _w((lambda *s: torch.randn(*s, dtype=torch.bfloat16) * 0.05)(K, C, C) * (1.0 / (K * C) ** 0.5)),
        "mean": _w((lambda *s: torch.randn(*s, dtype=torch.bfloat16) * 0.05)(C) * 0.1),
        "var": _w(torch.abs((lambda *s: torch.randn(*s, dtype=torch.bfloat16) * 0.05)(C)) + 0.5),
        "g": _w((lambda *s: torch.randn(*s, dtype=torch.bfloat16) * 0.05)(C) + 1.0),
        "b": _w((lambda *s: torch.randn(*s, dtype=torch.bfloat16) * 0.05)(C) * 0.1),
    }

def reference(x, w, mean, var, g, b):
    K = 3
    P = K // 2
    S = x.shape[1]
    xp = _pad(x, ((0, 0), (P, P), (0, 0)))
    y = sum(torch.einsum('bsc,cd->bsd', xp[:, k:k + S, :], w[k]) for k in range(K))
    inv_std = 1.0 / torch.sqrt(var + 1e-5)
    y = (y - mean) * (g * inv_std) + b
    return _silu(y)
```

```cpp
#include <cuda_runtime.h>
#include <cuda_bf16.h>
#include <cuda.h>
#include <stdint.h>

namespace {

constexpr int CH = 448;
constexpr int NBATCH = 1024;
constexpr int NCTA = 128;
constexpr int XSLOT = 16384;
constexpr int NX = 9;
constexpr int WBYTES = 14336;
#define OPT_A 0
#define OPT_B 0
#define OPT_C 0
constexpr int NW = 5;
constexpr int NSTAGE = 112;
constexpr uint32_t SBASE = 1024;
constexpr uint32_t A_X = SBASE;
constexpr uint32_t A_W = A_X + NX * XSLOT;
constexpr uint32_t A_DUMMY = A_W + NW * WBYTES;
constexpr uint32_t A_PAR = A_DUMMY + 2048;
constexpr uint32_t A_WBAR = A_PAR + 896 + 16;
constexpr uint32_t A_XBAR = A_WBAR + 16 * (NSTAGE + 5);
constexpr int SMEM_BYTES = (A_XBAR + 8 * 31) - SBASE;
constexpr int NUNITS = 784;

constexpr int NSCR = 56;
__device__ uint4 g_wscratch[2 * NSCR * WBYTES / 16];
__device__ unsigned int g_counters[2];
#define TS(i)

__device__ __forceinline__ void wgmma_n224(float (&d)[112], uint32_t a0, uint32_t a1, uint32_t a2, uint32_t a3, uint64_t descB) {
  asm volatile(
    "wgmma.mma_async.sync.aligned.m64n224k16.f32.bf16.bf16 {"
    "%0, %1, %2, %3, %4, %5, %6, %7, %8, %9, %10, %11, %12, %13, %14, %15, "
    "%16, %17, %18, %19, %20, %21, %22, %23, %24, %25, %26, %27, %28, %29, %30, %31, "
    "%32, %33, %34, %35, %36, %37, %38, %39, %40, %41, %42, %43, %44, %45, %46, %47, "
    "%48, %49, %50, %51, %52, %53, %54, %55, %56, %57, %58, %59, %60, %61, %62, %63, "
    "%64, %65, %66, %67, %68, %69, %70, %71, %72, %73, %74, %75, %76, %77, %78, %79, "
    "%80, %81, %82, %83, %84, %85, %86, %87, %88, %89, %90, %91, %92, %93, %94, %95, "
    "%96, %97, %98, %99, %100, %101, %102, %103, %104, %105, %106, %107, %108, %109, %110, %111}, "
    "{%112, %113, %114, %115}, %116, 1, 1, 1, 1;\n"
    : "+f"(d[0]), "+f"(d[1]), "+f"(d[2]), "+f"(d[3]), "+f"(d[4]), "+f"(d[5]), "+f"(d[6]), "+f"(d[7]),
      "+f"(d[8]), "+f"(d[9]), "+f"(d[10]), "+f"(d[11]), "+f"(d[12]), "+f"(d[13]), "+f"(d[14]), "+f"(d[15]),
      "+f"(d[16]), "+f"(d[17]), "+f"(d[18]), "+f"(d[19]), "+f"(d[20]), "+f"(d[21]), "+f"(d[22]), "+f"(d[23]),
      "+f"(d[24]), "+f"(d[25]), "+f"(d[26]), "+f"(d[27]), "+f"(d[28]), "+f"(d[29]), "+f"(d[30]), "+f"(d[31]),
      "+f"(d[32]), "+f"(d[33]), "+f"(d[34]), "+f"(d[35]), "+f"(d[36]), "+f"(d[37]), "+f"(d[38]), "+f"(d[39]),
      "+f"(d[40]), "+f"(d[41]), "+f"(d[42]), "+f"(d[43]), "+f"(d[44]), "+f"(d[45]), "+f"(d[46]), "+f"(d[47]),
      "+f"(d[48]), "+f"(d[49]), "+f"(d[50]), "+f"(d[51]), "+f"(d[52]), "+f"(d[53]), "+f"(d[54]), "+f"(d[55]),
      "+f"(d[56]), "+f"(d[57]), "+f"(d[58]), "+f"(d[59]), "+f"(d[60]), "+f"(d[61]), "+f"(d[62]), "+f"(d[63]),
      "+f"(d[64]), "+f"(d[65]), "+f"(d[66]), "+f"(d[67]), "+f"(d[68]), "+f"(d[69]), "+f"(d[70]), "+f"(d[71]),
      "+f"(d[72]), "+f"(d[73]), "+f"(d[74]), "+f"(d[75]), "+f"(d[76]), "+f"(d[77]), "+f"(d[78]), "+f"(d[79]),
      "+f"(d[80]), "+f"(d[81]), "+f"(d[82]), "+f"(d[83]), "+f"(d[84]), "+f"(d[85]), "+f"(d[86]), "+f"(d[87]),
      "+f"(d[88]), "+f"(d[89]), "+f"(d[90]), "+f"(d[91]), "+f"(d[92]), "+f"(d[93]), "+f"(d[94]), "+f"(d[95]),
      "+f"(d[96]), "+f"(d[97]), "+f"(d[98]), "+f"(d[99]), "+f"(d[100]), "+f"(d[101]), "+f"(d[102]), "+f"(d[103]),
      "+f"(d[104]), "+f"(d[105]), "+f"(d[106]), "+f"(d[107]), "+f"(d[108]), "+f"(d[109]), "+f"(d[110]), "+f"(d[111])
    : "r"(a0), "r"(a1), "r"(a2), "r"(a3), "l"(descB));
}
__device__ __forceinline__ void wgmma_n224_p(float (&d)[112], uint32_t a0, uint32_t a1, uint32_t a2, uint32_t a3, uint64_t descB, int scale_d) {
  asm volatile(
    "{\n.reg .pred p;\nsetp.ne.b32 p, %117, 0;\n"
    "wgmma.mma_async.sync.aligned.m64n224k16.f32.bf16.bf16 {"
    "%0, %1, %2, %3, %4, %5, %6, %7, %8, %9, %10, %11, %12, %13, %14, %15, "
    "%16, %17, %18, %19, %20, %21, %22, %23, %24, %25, %26, %27, %28, %29, %30, %31, "
    "%32, %33, %34, %35, %36, %37, %38, %39, %40, %41, %42, %43, %44, %45, %46, %47, "
    "%48, %49, %50, %51, %52, %53, %54, %55, %56, %57, %58, %59, %60, %61, %62, %63, "
    "%64, %65, %66, %67, %68, %69, %70, %71, %72, %73, %74, %75, %76, %77, %78, %79, "
    "%80, %81, %82, %83, %84, %85, %86, %87, %88, %89, %90, %91, %92, %93, %94, %95, "
    "%96, %97, %98, %99, %100, %101, %102, %103, %104, %105, %106, %107, %108, %109, %110, %111}, "
    "{%112, %113, %114, %115}, %116, p, 1, 1, 1;\n}\n"
    : "+f"(d[0]), "+f"(d[1]), "+f"(d[2]), "+f"(d[3]), "+f"(d[4]), "+f"(d[5]), "+f"(d[6]), "+f"(d[7]),
      "+f"(d[8]), "+f"(d[9]), "+f"(d[10]), "+f"(d[11]), "+f"(d[12]), "+f"(d[13]), "+f"(d[14]), "+f"(d[15]),
      "+f"(d[16]), "+f"(d[17]), "+f"(d[18]), "+f"(d[19]), "+f"(d[20]), "+f"(d[21]), "+f"(d[22]), "+f"(d[23]),
      "+f"(d[24]), "+f"(d[25]), "+f"(d[26]), "+f"(d[27]), "+f"(d[28]), "+f"(d[29]), "+f"(d[30]), "+f"(d[31]),
      "+f"(d[32]), "+f"(d[33]), "+f"(d[34]), "+f"(d[35]), "+f"(d[36]), "+f"(d[37]), "+f"(d[38]), "+f"(d[39]),
      "+f"(d[40]), "+f"(d[41]), "+f"(d[42]), "+f"(d[43]), "+f"(d[44]), "+f"(d[45]), "+f"(d[46]), "+f"(d[47]),
      "+f"(d[48]), "+f"(d[49]), "+f"(d[50]), "+f"(d[51]), "+f"(d[52]), "+f"(d[53]), "+f"(d[54]), "+f"(d[55]),
      "+f"(d[56]), "+f"(d[57]), "+f"(d[58]), "+f"(d[59]), "+f"(d[60]), "+f"(d[61]), "+f"(d[62]), "+f"(d[63]),
      "+f"(d[64]), "+f"(d[65]), "+f"(d[66]), "+f"(d[67]), "+f"(d[68]), "+f"(d[69]), "+f"(d[70]), "+f"(d[71]),
      "+f"(d[72]), "+f"(d[73]), "+f"(d[74]), "+f"(d[75]), "+f"(d[76]), "+f"(d[77]), "+f"(d[78]), "+f"(d[79]),
      "+f"(d[80]), "+f"(d[81]), "+f"(d[82]), "+f"(d[83]), "+f"(d[84]), "+f"(d[85]), "+f"(d[86]), "+f"(d[87]),
      "+f"(d[88]), "+f"(d[89]), "+f"(d[90]), "+f"(d[91]), "+f"(d[92]), "+f"(d[93]), "+f"(d[94]), "+f"(d[95]),
      "+f"(d[96]), "+f"(d[97]), "+f"(d[98]), "+f"(d[99]), "+f"(d[100]), "+f"(d[101]), "+f"(d[102]), "+f"(d[103]),
      "+f"(d[104]), "+f"(d[105]), "+f"(d[106]), "+f"(d[107]), "+f"(d[108]), "+f"(d[109]), "+f"(d[110]), "+f"(d[111])
    : "r"(a0), "r"(a1), "r"(a2), "r"(a3), "l"(descB), "r"(scale_d));
}

__device__ __forceinline__ void mbar_init(uint32_t b, int c) {
  asm volatile("mbarrier.init.shared::cta.b64 [%0], %1;" ::"r"(b), "r"(c) : "memory");
}
#define ELECT_P "{\n.reg .pred p;\nelect.sync _|p, 0xffffffff;\n"
__device__ __forceinline__ void mbar_arrive(uint32_t b) {
  asm volatile(ELECT_P "@p mbarrier.arrive.shared::cta.b64 _, [%0];\n}\n" ::"r"(b) : "memory");
}
__device__ __forceinline__ uint32_t mbar_try(uint32_t b) {
  uint32_t ok;
  asm volatile("{\n.reg .pred p;\nmbarrier.try_wait.parity.shared::cta.b64 p, [%1], 0;\nselp.u32 %0, 1, 0, p;\n}\n"
               : "=r"(ok) : "r"(b) : "memory");
  return ok;
}
__device__ __forceinline__ void mbar_wait(uint32_t b) {
  uint32_t n = 0;
  while (!__all_sync(0xffffffffu, mbar_try(b)) && ++n < (1u << 20)) {}
}
__device__ __forceinline__ void tma_load_4d(uint32_t dst, const CUtensorMap* m, int c0, int c1, int c2, int c3, uint32_t bar, int bytes) {
  asm volatile(ELECT_P "@p mbarrier.arrive.expect_tx.shared::cta.b64 _, [%6], %7;\n"
               "@p cp.async.bulk.tensor.4d.shared::cluster.global.mbarrier::complete_tx::bytes [%0], [%1, {%2, %3, %4, %5}], [%6];\n}\n"
               ::"r"(dst), "l"(m), "r"(c0), "r"(c1), "r"(c2), "r"(c3), "r"(bar), "r"(bytes) : "memory");
}
__device__ __forceinline__ void tma_prefetch_4d(const CUtensorMap* m, int c0, int c1, int c2, int c3) {
  asm volatile(ELECT_P "@p cp.async.bulk.prefetch.tensor.4d.L2.global [%0, {%1, %2, %3, %4}];\n}\n"
               ::"l"(m), "r"(c0), "r"(c1), "r"(c2), "r"(c3) : "memory");
}
__device__ __forceinline__ void tma_load_3d(uint32_t dst, const CUtensorMap* m, int c0, int c1, int c2, uint32_t bar, int bytes) {
  asm volatile(ELECT_P "@p mbarrier.arrive.expect_tx.shared::cta.b64 _, [%5], %6;\n"
               "@p cp.async.bulk.tensor.3d.shared::cluster.global.mbarrier::complete_tx::bytes [%0], [%1, {%2, %3, %4}], [%5];\n}\n"
               ::"r"(dst), "l"(m), "r"(c0), "r"(c1), "r"(c2), "r"(bar), "r"(bytes) : "memory");
}
__device__ __forceinline__ void bulk_load(uint32_t dst, const void* src, int bytes, uint32_t bar) {
  asm volatile(ELECT_P "@p mbarrier.arrive.expect_tx.shared::cta.b64 _, [%3], %2;\n"
               "@p cp.async.bulk.shared::cluster.global.mbarrier::complete_tx::bytes [%0], [%1], %2, [%3];\n}\n"
               ::"r"(dst), "l"(src), "r"(bytes), "r"(bar) : "memory");
}
__device__ __forceinline__ void bulk_store(void* dst, uint32_t src, int bytes) {
  asm volatile(ELECT_P "@p cp.async.bulk.global.shared::cta.bulk_group [%0], [%1], %2;\n}\n"
               ::"l"(dst), "r"(src), "r"(bytes) : "memory");
}
__device__ __forceinline__ void tma_store_4d(const CUtensorMap* m, uint32_t src, int c0, int c1, int c2, int c3) {
  asm volatile(ELECT_P "@p cp.async.bulk.tensor.4d.global.shared::cta.bulk_group [%0, {%2, %3, %4, %5}], [%1];\n}\n"
               "cp.async.bulk.commit_group;\n"
               ::"l"(m), "r"(src), "r"(c0), "r"(c1), "r"(c2), "r"(c3) : "memory");
}
#define FENCE_ASYNC_SMEM() asm volatile("fence.proxy.async.shared::cta;" ::: "memory")
__device__ __forceinline__ void ldsm4(uint32_t (&r)[4], uint32_t a) {
  asm volatile("ldmatrix.sync.aligned.m8n8.x4.shared.b16 {%0,%1,%2,%3}, [%4];"
               : "=r"(r[0]), "=r"(r[1]), "=r"(r[2]), "=r"(r[3]) : "r"(a) : "memory");
}
__device__ __forceinline__ void ldsm4_if(uint32_t (&r)[4], uint32_t a, uint32_t pred) {
  asm volatile("{\n.reg .pred p;\nsetp.ne.u32 p, %5, 0;\n@p ldmatrix.sync.aligned.m8n8.x4.shared.b16 {%0,%1,%2,%3}, [%4];\n}\n"
               : "+r"(r[0]), "+r"(r[1]), "+r"(r[2]), "+r"(r[3]) : "r"(a), "r"(pred) : "memory");
}
__device__ __forceinline__ void stsm4(uint32_t a, uint32_t r0, uint32_t r1, uint32_t r2, uint32_t r3) {
  asm volatile("stmatrix.sync.aligned.m8n8.x4.shared.b16 [%0], {%1,%2,%3,%4};" ::"r"(a), "r"(r0), "r"(r1), "r"(r2), "r"(r3) : "memory");
}
__device__ __forceinline__ void sts128(uint32_t a, uint32_t r0, uint32_t r1, uint32_t r2, uint32_t r3) {
  asm volatile("st.shared.v4.u32 [%0], {%1,%2,%3,%4};" ::"r"(a), "r"(r0), "r"(r1), "r"(r2), "r"(r3) : "memory");
}
__device__ __forceinline__ void lds128(uint32_t* r, uint32_t a) {
  asm volatile("ld.shared.v4.u32 {%0,%1,%2,%3}, [%4];" : "=r"(r[0]), "=r"(r[1]), "=r"(r[2]), "=r"(r[3]) : "r"(a) : "memory");
}
__device__ __forceinline__ uint32_t hfma2(uint32_t a, uint32_t b, uint32_t c) {
  uint32_t d; asm volatile("fma.rn.bf16x2 %0, %1, %2, %3;" : "=r"(d) : "r"(a), "r"(b), "r"(c)); return d;
}
__device__ __forceinline__ uint32_t lane_id() { uint32_t l; asm volatile("mov.u32 %0, %%laneid;" : "=r"(l)); return l; }
__device__ __forceinline__ float bf_lo(uint32_t v) { return __uint_as_float(v << 16); }
__device__ __forceinline__ float bf_hi(uint32_t v) { return __uint_as_float(v & 0xffff0000u); }
__device__ __forceinline__ uint32_t hsub2(uint32_t a, uint32_t b) {
  uint32_t d; asm volatile("sub.rn.bf16x2 %0, %1, %2;" : "=r"(d) : "r"(a), "r"(b)); return d;
}
__device__ __forceinline__ uint32_t hadd2(uint32_t a, uint32_t b) {
  uint32_t d; asm volatile("add.rn.bf16x2 %0, %1, %2;" : "=r"(d) : "r"(a), "r"(b)); return d;
}
__device__ __forceinline__ uint32_t pack_bf16(float lo, float hi) {
  uint32_t d; asm("cvt.rn.bf16x2.f32 %0, %1, %2;" : "=r"(d) : "f"(hi), "f"(lo)); return d;
}
__device__ __forceinline__ float silu_half(float h) {
  float t; asm("tanh.approx.f32 %0, %1;" : "=f"(t) : "f"(h)); return fmaf(h, t, h);
}
#define WG_FENCE() asm volatile("wgmma.fence.sync.aligned;" ::: "memory")
#define WG_COMMIT() asm volatile("wgmma.commit_group.sync.aligned;" ::: "memory")
#define STR2(x) #x
#define STR(x) STR2(x)
#define WG_WAIT0() asm volatile("wgmma.wait_group.sync.aligned 0; // L" STR(__LINE__) ::: "memory")
#define WG_WAIT1() asm volatile("wgmma.wait_group.sync.aligned 1;" ::: "memory")

constexpr uint32_t WD0 = (A_W >> 4) | (128u << 16);
__device__ __forceinline__ uint64_t wdesc(uint32_t wd) { return ((uint64_t)(32u | (2u << 30)) << 32) | wd; }

struct Params {
  const __nv_bfloat16* w;
  const __nv_bfloat16* mean;
  const __nv_bfloat16* var;
  const __nv_bfloat16* g;
  const __nv_bfloat16* b;
  char* scratch;
  unsigned int* counters;
};

struct Ctx {
  const CUtensorMap* mx; const CUtensorMap* mw; const CUtensorMap* mo;
  const char* scratch;
  int half, b0, warp;
};

__device__ __forceinline__ void w_load_raw(const Ctx& c, uint32_t wa, int t, uint32_t bar) {
  tma_load_3d(wa, c.mw, 0, 32 * t, 7 * c.half, bar, WBYTES);
}
__device__ __forceinline__ void w_load_scratch(const Ctx& c, uint32_t wa, int t, uint32_t bar) {
  bulk_load(wa, c.scratch + t * WBYTES, WBYTES, bar);
}
__device__ __forceinline__ unsigned int ld_ready(const unsigned int* ready) {
  unsigned int v;
  asm volatile("ld.relaxed.gpu.global.u32 %0, [%1];" : "=r"(v) : "l"(ready) : "memory");
  return v;
}
__device__ __forceinline__ uint32_t xnext(uint32_t s) { return s == NX - 1 ? 0 : s + 1; }
__device__ __forceinline__ uint32_t xprev(uint32_t s) { return s == 0 ? NX - 1 : s - 1; }
__device__ __forceinline__ void x_load(const Ctx& c, uint32_t slot, int chunk, int pass, int odd) {
  tma_load_4d(A_X + slot * XSLOT, c.mx, 64 * chunk, c.b0 + 8 * pass, 0, odd, A_XBAR + 8 * (15 * pass + 7 * (1 - odd) + chunk),
              XSLOT);
}

template <int I> struct IC { static constexpr int v = I; };
template <int N, int I = 0, class F>
__device__ __forceinline__ void static_for(F&& f) {
  if constexpr (I < N) { f(IC<I>{}); static_for<N, I + 1>(f); }
}
__device__ __forceinline__ uint32_t silu2(uint32_t h) { return pack_bf16(silu_half(bf_lo(h)), silu_half(bf_hi(h))); }

constexpr uint32_t WDSTEP = WBYTES / 16;
__device__ __forceinline__ uint32_t wd_next(uint32_t wd) { return wd == WD0 + (NW - 1) * WDSTEP ? WD0 : wd + WDSTEP; }
__device__ __forceinline__ uint32_t wd_refill_addr(uint32_t wd) {
  return ((wd < WD0 + 2 * WDSTEP ? wd + 3 * WDSTEP : wd - 2 * WDSTEP) & 0xffffu) << 4;
}

__global__ void __launch_bounds__(256, 1)
conv_bn_silu_kernel(const __grid_constant__ CUtensorMap mx, const __grid_constant__ CUtensorMap mw,
                    const __grid_constant__ CUtensorMap mo, const Params prm) {
  extern __shared__ __align__(1024) char smem_raw[];
  const int tid = threadIdx.x;
  Ctx c;
  c.mx = &mx; c.mw = &mw; c.mo = &mo;
  c.half = blockIdx.x & 1;
  c.b0 = (blockIdx.x >> 1) * 16;
  c.warp = __shfl_sync(0xffffffff, tid >> 5, 0);
  c.scratch = prm.scratch + c.half * (NSCR * WBYTES);
  const int one = gridDim.y;

  TS(0);
  const int unit = blockIdx.x * 7 + c.warp - 1;
  const bool has_unit = c.warp != 0 && unit < NUNITS;
  const int ug = unit / 56, uc = unit - ug * 56;
  uint32_t pk[56];
#pragma unroll
  for (int i = 0; i < 56; i++) pk[i] = 0;
  if (c.warp != 0) {
    if ((tid & 31) == 0) {
      const uint32_t bar = A_WBAR + 16 * (c.warp * 16 - 11);
#pragma unroll
      for (int i = 0; i < 16; i++) { mbar_init(bar + 16 * i, 1); mbar_init(bar + 16 * i + 8, 8); }
#pragma unroll
      for (int i = 0; i < 4; i++) mbar_init(A_XBAR + 8 * (c.warp * 4 - 1 + i), 1);
      if (c.warp == 7) asm volatile("mbarrier.arrive.shared::cta.b64 _, [%0];" ::"r"(A_WBAR + 16 * NSTAGE) : "memory");
      FENCE_ASYNC_SMEM();
    }
    __syncwarp();
    if (has_unit) {
      const uint4* wp = (const uint4*)(prm.w + (uc * 8 + ((tid >> 2) & 7)) * CH + ug * 32) + (tid & 3);
#pragma unroll
      for (int k = 0; k < 3; k++) {
        const uint4 v = __ldg(wp + k * (CH * CH / 8));
        pk[4 * k] = v.x; pk[4 * k + 1] = v.y; pk[4 * k + 2] = v.z; pk[4 * k + 3] = v.w;
      }
    }
    const int col = c.half * 224 + tid - 32;
    pk[12] = __ldg((const unsigned short*)prm.var + col);
    pk[13] = __ldg((const unsigned short*)prm.g + col);
    pk[14] = __ldg((const unsigned short*)prm.mean + col);
    pk[15] = __ldg((const unsigned short*)prm.b + col);
  } else {
    if (tid == 0) {
      if ((uint32_t)__cvta_generic_to_shared(smem_raw) != SBASE) __trap();
#pragma unroll
      for (int i = 0; i < 3; i++) mbar_init(A_XBAR + 8 * i, 1);
#pragma unroll
      for (int i = -1; i < 5; i++) { mbar_init(A_WBAR + 16 * i, 1); mbar_init(A_WBAR + 16 * i + 8, 8); }
      FENCE_ASYNC_SMEM();
    }
    __syncwarp();
    x_load(c, 0, 0, 0, 1); w_load_raw(c, A_W, 0, A_WBAR); w_load_raw(c, A_W + WBYTES, 1, A_WBAR + 16);
    x_load(c, 1, 1, 0, 1); w_load_raw(c, A_W + 2 * WBYTES, 2, A_WBAR + 32); w_load_raw(c, A_W + 3 * WBYTES, 3, A_WBAR + 48);
    x_load(c, 2, 2, 0, 1); w_load_raw(c, A_W + 4 * WBYTES, 4, A_WBAR + 64);
  }
  __syncthreads();

  auto setup_work = [&]() {
    const uint32_t l = lane_id();
    if (has_unit) {
      const uint32_t sb = A_X + 8 * XSLOT + c.warp * 2048, sa = sb + (l >> 2) * 64 + (((l & 3) ^ ((l >> 3) & 3)) << 4);
      uint32_t o1[4], o2[4], o3[4];
#pragma unroll
      for (int k = 0; k < 4; k++) {
        const uint32_t g0 = pk[k], g1 = pk[4 + k], g2 = pk[8 + k];
        const float sl = bf_lo(g0) + bf_lo(g2), sh = bf_hi(g0) + bf_hi(g2);
        o1[k] = pack_bf16(sl + bf_lo(g1), sh + bf_hi(g1));
        o2[k] = pack_bf16(sl - bf_lo(g1), sh - bf_hi(g1));
        o3[k] = pack_bf16(-2.f * bf_lo(g2), -2.f * bf_hi(g2));
      }
      sts128(sa, o1[0], o1[1], o1[2], o1[3]);
      sts128(sa + 512, o2[0], o2[1], o2[2], o2[3]);
      sts128(sa + 1024, o3[0], o3[1], o3[2], o3[3]);
      sts128(sa + 1536, pk[0], pk[1], pk[2], pk[3]);
      FENCE_ASYNC_SMEM();
      __syncwarp();
      const int h = ug >= 7 ? 1 : 0;
      char* base = prm.scratch + h * (NSCR * WBYTES) + (ug - 7 * h) * 2048;
      char* pT = base + (14 + (uc >> 1)) * WBYTES + (uc & 1) * 512;
      char* pE = base + (uc >> 2) * WBYTES + (uc & 3) * 512;
      bulk_store(pT, sb, 512);
      bulk_store(pT + 1024, sb + 512, 512);
      bulk_store(pE + 42 * WBYTES, sb + 1024, 512);
      bulk_store(pE, sb + 1536, 512);
      asm volatile("cp.async.bulk.commit_group;" ::: "memory");
    }
    if (c.warp != 0) {
      const int pt = c.warp * 32 + l - 32;
      const float sc = bf_lo(pack_bf16(bf_lo(pk[13]) * rsqrtf(bf_lo(pk[12]) + 1e-5f), 0.f));
      const float sh = fmaf(-bf_lo(pk[14]), sc, bf_lo(pk[15]));
      const uint32_t word = pack_bf16(0.25f * sc, 0.5f * sh);
      const uint32_t pa = A_PAR + (pt >> 4) * 64 + ((pt >> 1) & 3) * 16 + ((pt >> 3) & 1) * 4 + (pt & 1) * 2;
      asm volatile("st.shared.u16 [%0], %1;" ::"r"(pa), "h"((uint16_t)word) : "memory");
      asm volatile("st.shared.u16 [%0], %1;" ::"r"(pa + 8), "h"((uint16_t)(word >> 16)) : "memory");
    }
    __syncwarp();
  };

  float accA[112], accB[112];
#pragma unroll
  for (int i = 0; i < 112; i++) accA[i] = 0.f;
  uint32_t wd = WD0;
  uint32_t wb = A_WBAR;
  uint32_t xs = 0;
  uint32_t lane_stg, lane_par;
  TS(1);
  mbar_wait(A_WBAR);

#pragma unroll 1
  for (int e = 0; e < 4; e++) {
    const int p3 = e & 1, pass = e >> 1;
    const uint32_t xs0 = xs;
    if (one) {
      const uint32_t xb = A_XBAR + 8 * (15 * pass + 7 * p3);
      const uint32_t stg = e ? A_X + (e == 3 ? 2 : 5) * XSLOT + c.warp * 2048 : A_DUMMY;
      const uint32_t stg2[2] = {stg + (p3 ^ 1) * 1024, stg + p3 * 1024};
      const uint32_t ld0 = p3 | c.warp, ld2 = (p3 ^ 1) | (c.warp ^ 7);
      const int ob = e ? c.b0 + 8 * ((e - 1) >> 1) : NBATCH;
      uint32_t lane_e;
      {
        const uint32_t l = lane_id(), mi = l >> 3, row = l & 7;
        lane_e = A_X + (2 * c.warp + p3) * 1024 + row * 128 + ((mi ^ row) << 4);
        lane_stg = (mi & 1) * 512 + row * 64 + (((mi >> 1) ^ ((row >> 1) & 3)) << 4);
        lane_par = A_PAR + (l & 3) * 16;
      }
      uint32_t q0[4] = {0, 0, 0, 0}, q1[4], q2[4] = {0, 0, 0, 0}, f[8], par[4], hq[4], ready = 0;
      auto loads = [&](uint32_t ad) {
        ldsm4_if(q0, ad - 1024, ld0);
        ldsm4(q1, ad);
        ldsm4_if(q2, ad + 1024, ld2);
      };
      auto frags = [&]() {
#pragma unroll
        for (int i = 0; i < 4; i++) { f[2 * i] = hsub2(q0[i], q1[i]); f[2 * i + 1] = hsub2(q1[i], q2[i]); }
      };
      auto bn = [&](auto J) {
#pragma unroll
        for (int i = 0; i < 4; i++) hq[i] = hfma2(pk[4 * J.v + i], par[i >> 1], par[2 + (i >> 1)]);
      };
      mbar_wait(xb);
      if (e == 0) TS(2);
      uint32_t xa = lane_e + xs * XSLOT;
      loads(xa);
      lds128(par, lane_par);
      frags();
      bn(IC<0>{});
      loads(xa ^ 64);
      lds128(par, lane_par + 64);

      static_for<14>([&](auto J) {
        constexpr int j = J.v, h = j & 1, ch = j >> 1;
        const uint32_t eb = wb + 16 * j - 8, fb = wb + 16 * j + 16, wdc = wd;
        constexpr bool probe_x = h == 0 && ch < 6;
        uint32_t ok;
        auto probes = [&]() {
          ok = mbar_try(fb);
          if constexpr (probe_x) ok &= mbar_try(xb + 8 * ch + 8);
          ok &= mbar_try(eb);
        };
        auto producer = [&]() {
          if (j < 11 && e == 0) {
            if (j >= 2) w_load_raw(c, wd_refill_addr(wdc), j + 3, wb + 16 * j + 48);
            if (h == 1 && ch < 5) x_load(c, ch + 3, ch < 4 ? ch + 3 : 0, 0, ch < 4 ? 1 : 0);
          } else if (j < 11 || e != 3) {
            w_load_scratch(c, wd_refill_addr(wdc), j + 3 + 42 * p3 - (j >= 11 ? 56 * p3 : 0), wb + 16 * j + 48);
            if (h == 0 && e == 1) x_load(c, (6 + ch) % 9, ch, 1, 1);
            if (j == 0 && e == 2) x_load(c, 4, 0, 1, 0);
            if (j == 11 && e == 0) x_load(c, 8, 1, 0, 0);
            if (j == 11 && e == 2) tma_prefetch_4d(c.mx, 64, c.b0 + 8, 0, 0);
            if (j == 13 && !p3) tma_prefetch_4d(c.mx, 128, c.b0 + 8 * pass, 0, 0);
          }
        };
        if constexpr (OPT_C == 1) {
          mbar_arrive(eb);
          probes();
          if constexpr (OPT_A == 1 && h == 0 && ch > 0) FENCE_ASYNC_SMEM();
        }
        WG_FENCE();
        if constexpr (j == 0) wgmma_n224_p(accA, f[0], f[1], f[2], f[3], wdesc(wd), p3);
        else wgmma_n224(accA, f[0], f[1], f[2], f[3], wdesc(wd));
        wgmma_n224(accA, f[4], f[5], f[6], f[7], wdesc(wd + 64));
        WG_COMMIT();
        if constexpr (OPT_C == 0) mbar_arrive(eb);
        if constexpr (OPT_B == 0) { if (__builtin_expect(c.warp == (h ? 5 : 1), 0)) producer(); }
        if constexpr (j == 0) { if (e == 0) setup_work(); }
        if constexpr (j == 4) {
          if (e == 0) {
            asm volatile("cp.async.bulk.wait_group 0;" ::: "memory");
            if (has_unit) asm volatile(ELECT_P "@p red.relaxed.gpu.global.add.u32 [%0], 1;\n}\n" ::"l"(prm.counters) : "memory");
          }
        }
        if constexpr (j == 9) ready = ld_ready(prm.counters);
        wd = wd_next(wd);
        if constexpr (h == 0) { xs = xnext(xs); xa = lane_e + xs * XSLOT; }
        if constexpr (OPT_C == 0) {
          probes();
          if constexpr (OPT_A == 1 && h == 0 && ch > 0) FENCE_ASYNC_SMEM();
        }
        const uint32_t p0 = silu2(hq[0]), p1 = silu2(hq[1]), p2 = silu2(hq[2]), p3v = silu2(hq[3]);
        if constexpr (h == 0) {
          if constexpr (ch > 0) {
            __syncwarp();
            tma_store_4d(c.mo, stg2[(ch - 1) & 1], c.half * 224 + (ch - 1) * 32, ob, 2 * c.warp, p3 ^ 1);
          }
          asm volatile("cp.async.bulk.wait_group.read 1;" ::: "memory");
          __syncwarp();
        }
        stsm4(stg2[ch & 1] + (lane_stg ^ (h << 5)), p0, p1, p2, p3v);
        if constexpr ((OPT_A == 0 && h == 1) || j == 13) FENCE_ASYNC_SMEM();
        if constexpr (j < 13) { frags(); bn(IC<(j < 13 ? j + 1 : 0)>{}); }
        if constexpr (j == 13) {
          __syncwarp();
          tma_store_4d(c.mo, stg2[0], c.half * 224 + 6 * 32, ob, 2 * c.warp, p3 ^ 1);
        }
        if constexpr (j == 10) ok &= ready >= NUNITS || e != 0;
        const bool prod = OPT_B == 1 && c.warp == (h ? 5 : 1);
        if (__builtin_expect(!__all_sync(0xffffffffu, ok) || prod, 0)) {
          if (prod) producer();
          uint32_t n = 0;
          while (!__all_sync(0xffffffffu, ok) && ++n < (1u << 20)) {
            ok = mbar_try(fb) & mbar_try(eb);
            if constexpr (probe_x) ok &= mbar_try(xb + 8 * ch + 8);
            if constexpr (j == 10) ok &= e != 0 || ld_ready(prm.counters) >= NUNITS;
          }
        }
        if constexpr (j == 10) asm volatile("fence.proxy.async.global;" ::: "memory");
        if constexpr (j < 12) {
          loads(h ? xa ^ 64 : xa);
          lds128(par, lane_par + (j + 2) * 64);
        }
        WG_WAIT0();
      });
      wb += 16 * 14;
    }
    TS(p3 ? 7 + 5 * pass : 3 + 5 * pass);
    if (p3) {
      if (e == 3) break;
      xs = xnext(xs);
      WG_WAIT0();
#pragma unroll
      for (int i = 0; i < 56; i++)
        asm volatile("cvt.rn.bf16x2.f32 %0, %2, %1;" : "=r"(pk[i]) : "f"(accA[2 * i]), "f"(accA[2 * i + 1]));
      continue;
    }
    uint32_t xo = xs0;
    uint32_t lane_t;
    {
      const uint32_t l = lane_id(), mi = l >> 3, row = l & 7;
      lane_t = A_X + (2 * c.warp + (mi >> 1)) * 1024 + row * 128 + (((mi & 1) ^ row) << 4);
    }
    uint32_t qe[4], qo[4], ae = lane_t + xs * XSLOT, ao = lane_t + xo * XSLOT;
    uint32_t xb = A_XBAR + 8 * (15 * pass + 7);
    mbar_wait(xb);
    ldsm4(qe, ae);
    ldsm4(qo, ao);
    WG_WAIT0();
#pragma unroll
    for (int i = 0; i < 112; i++) asm volatile("mov.b32 %0, %1;" : "=f"(accB[i]) : "f"(accA[i]));
    asm volatile("cp.async.bulk.wait_group.read 0;" ::: "memory");
    TS(4 + 5 * pass);
#pragma unroll 1
    for (int kc = 0; kc < 7 * one; kc++) {
      static_for<4>([&](auto KS) {
        constexpr int ks = KS.v;
        const uint32_t eb = wb + 16 * ks - 8, fb = wb + 16 * ks + 16;
        {
          const uint32_t a0 = hadd2(qe[0], qo[0]), a1 = hadd2(qe[2], qo[2]), a2 = hadd2(qe[1], qo[1]), a3 = hadd2(qe[3], qo[3]);
          WG_FENCE();
          wgmma_n224(accA, a0, a1, a2, a3, wdesc(wd));
          WG_COMMIT();
          mbar_arrive(eb);
          if (__builtin_expect(c.warp == ((ks & 1) ? 5 : 1), 0)) {
            w_load_scratch(c, wd_refill_addr(wd), 4 * kc + ks + 17, wb + 16 * ks + 48);
            if (ks == 0 && kc && kc < 6) x_load(c, xprev(xo), kc + 1, pass, 0);
            if (ks == 1 && kc == 0 && pass == 1) x_load(c, 5, 1, 1, 0);
            if (ks == 3 && kc < 4) tma_prefetch_4d(c.mx, 64 * (kc + 3), c.b0 + 8 * pass, 0, 0);
          }
          if constexpr (ks == 3) {
            xo = xnext(xo);
            xs = xnext(xs);
            ae = lane_t + xs * XSLOT;
            ao = lane_t + xo * XSLOT;
          }
          WG_WAIT0();
        }
        {
          const uint32_t a0 = hsub2(qo[0], qe[0]), a1 = hsub2(qo[2], qe[2]), a2 = hsub2(qo[1], qe[1]), a3 = hsub2(qo[3], qe[3]);
          WG_FENCE();
          wgmma_n224(accB, a0, a1, a2, a3, wdesc(wd + 64));
          WG_COMMIT();
          wd = wd_next(wd);
          if constexpr (ks == 2) xb += kc < 6 ? 8 : 0;
          uint32_t ok = mbar_try(fb) & mbar_try(eb);
          if constexpr (ks == 2) ok &= mbar_try(xb);
          ldsm4(qe, ae ^ (((ks + 1) & 3) << 5));
          ldsm4(qo, ao ^ (((ks + 1) & 3) << 5));
          if (__builtin_expect(!__all_sync(0xffffffffu, ok), 0)) {
            uint32_t n = 0;
            do {
              ok = mbar_try(fb) & mbar_try(eb);
              if constexpr (ks == 2) ok &= mbar_try(xb);
            } while (!__all_sync(0xffffffffu, ok) && ++n < (1u << 20));
          }
          WG_WAIT0();
        }
      });
      wb += 16 * 4;
    }
    TS(5 + 5 * pass);
    xs = xo;
#pragma unroll
    for (int i = 0; i < 112; i++)
      asm volatile("sub.f32 %0, %0, %1;\nfma.rn.f32 %1, %1, 0f40000000, %0;\n" : "+f"(accA[i]), "+f"(accB[i]));
#pragma unroll
    for (int i = 0; i < 56; i++)
      asm volatile("cvt.rn.bf16x2.f32 %0, %2, %1;" : "=r"(pk[i]) : "f"(accB[2 * i]), "f"(accB[2 * i + 1]));
    TS(6 + 5 * pass);
  }
  WG_WAIT0();
  static_for<7>([&](auto CC) {
    constexpr int ch = CC.v;
    uint32_t par[8], p[8];
    lds128(par, lane_par + ch * 128);
    lds128(par + 4, lane_par + ch * 128 + 64);
#pragma unroll
    for (int i = 0; i < 8; i++) {
      const uint32_t sp = par[(i >> 2) * 4 + ((i >> 1) & 1)], tp = par[(i >> 2) * 4 + 2 + ((i >> 1) & 1)];
      p[i] = pack_bf16(silu_half(fmaf(accA[16 * ch + 2 * i], bf_lo(sp), bf_lo(tp))),
                       silu_half(fmaf(accA[16 * ch + 2 * i + 1], bf_hi(sp), bf_hi(tp))));
    }
    const uint32_t buf = A_X + 2 * XSLOT + c.warp * 2048 + ((ch + 1) & 1) * 1024;
    asm volatile("cp.async.bulk.wait_group.read 1;" ::: "memory");
    __syncwarp();
    stsm4(buf + lane_stg, p[0], p[1], p[2], p[3]);
    stsm4(buf + (lane_stg ^ 32), p[4], p[5], p[6], p[7]);
    FENCE_ASYNC_SMEM();
    __syncwarp();
    tma_store_4d(c.mo, buf, c.half * 224 + ch * 32, c.b0 + 8, 2 * c.warp, 1);
  });
  TS(13);
  asm volatile("cp.async.bulk.wait_group.read 0;" ::: "memory");
  TS(14);
  if (c.warp == 0 && lane_id() == 0) {
    const unsigned int d = atomicAdd(prm.counters + 1, 1);
    if (d == NCTA - 1) { prm.counters[0] = 0; prm.counters[1] = 0; __threadfence(); }
  }
}

typedef CUresult (*EncodeFn)(CUtensorMap*, CUtensorMapDataType, cuuint32_t, void*, const cuuint64_t*, const cuuint64_t*,
                             const cuuint32_t*, const cuuint32_t*, CUtensorMapInterleave, CUtensorMapSwizzle,
                             CUtensorMapL2promotion, CUtensorMapFloatOOBfill);

}

extern "C" void kernel_launch(void* const* d_in, const int* in_sizes, int n_in, void* d_out, int out_size) {
  static EncodeFn encode = nullptr;
  static void* scratch = nullptr;
  static void* counters = nullptr;
  if (!encode) {
    void* fn = nullptr;
    cudaDriverEntryPointQueryResult st;
    cudaGetDriverEntryPoint("cuTensorMapEncodeTiled", &fn, cudaEnableDefault, &st);
    encode = (EncodeFn)fn;
    cudaGetSymbolAddress(&scratch, g_wscratch);
    cudaGetSymbolAddress(&counters, g_counters);
    cudaFuncSetAttribute(conv_bn_silu_kernel, cudaFuncAttributeMaxDynamicSharedMemorySize, SMEM_BYTES);
  }
  CUtensorMap mx, mw, mo;
  const cuuint32_t ones[4] = {1, 1, 1, 1};
  {
    const cuuint64_t dims[4] = {CH, NBATCH, 16, 2};
    const cuuint64_t strides[3] = {32 * CH * 2, 2 * CH * 2, CH * 2};
    const cuuint32_t boxx[4] = {64, 8, 16, 1};
    encode(&mx, CU_TENSOR_MAP_DATA_TYPE_BFLOAT16, 4, d_in[0], dims, strides, boxx, ones, CU_TENSOR_MAP_INTERLEAVE_NONE,
           CU_TENSOR_MAP_SWIZZLE_128B, CU_TENSOR_MAP_L2_PROMOTION_L2_128B, CU_TENSOR_MAP_FLOAT_OOB_FILL_NONE);
    const cuuint32_t boxo[4] = {32, 8, 2, 1};
    encode(&mo, CU_TENSOR_MAP_DATA_TYPE_BFLOAT16, 4, d_out, dims, strides, boxo, ones, CU_TENSOR_MAP_INTERLEAVE_NONE,
           CU_TENSOR_MAP_SWIZZLE_64B, CU_TENSOR_MAP_L2_PROMOTION_NONE, CU_TENSOR_MAP_FLOAT_OOB_FILL_NONE);
  }
  {
    const cuuint64_t dims[3] = {32, CH, 14};
    const cuuint64_t strides[2] = {CH * 2, 64};
    const cuuint32_t box[3] = {32, 32, 7};
    encode(&mw, CU_TENSOR_MAP_DATA_TYPE_BFLOAT16, 3, d_in[1], dims, strides, box, ones, CU_TENSOR_MAP_INTERLEAVE_NONE,
           CU_TENSOR_MAP_SWIZZLE_64B, CU_TENSOR_MAP_L2_PROMOTION_L2_128B, CU_TENSOR_MAP_FLOAT_OOB_FILL_NONE);
  }
  Params prm;
  prm.w = (const __nv_bfloat16*)d_in[1];
  prm.mean = (const __nv_bfloat16*)d_in[2];
  prm.var = (const __nv_bfloat16*)d_in[3];
  prm.g = (const __nv_bfloat16*)d_in[4];
  prm.b = (const __nv_bfloat16*)d_in[5];
  prm.scratch = (char*)scratch;
  prm.counters = (unsigned int*)counters;
  conv_bn_silu_kernel<<<NCTA, 256, SMEM_BYTES>>>(mx, mw, mo, prm);
}
```

```cpp
#include <cuda_runtime.h>
#include <cuda_bf16.h>
#include <cuda.h>
#include <stdint.h>

namespace {

constexpr int CH = 448;
constexpr int NBATCH = 1024;
constexpr int NCTA = 128;
constexpr int XSLOT = 16384;
constexpr int NX = 9;
constexpr int WBYTES = 14336;
constexpr uint64_t EVICT_FIRST = 0x12F0000000000000ull;
constexpr int J_RDY = 7, J_PUB = 3, T2W = 3, BW = 6, TAILW = 3;
constexpr int WSLOT = 16384;
constexpr int NW = 5;
constexpr int NSTAGE = 112;
constexpr uint32_t SBASE = 1024;
constexpr uint32_t A_X = SBASE;
constexpr uint32_t A_W = A_X + NX * XSLOT;
constexpr uint32_t A_PAR = A_W + NW * WSLOT;
constexpr uint32_t A_WBAR = A_PAR + 896 + 16;
constexpr uint32_t A_XBAR = A_WBAR + 16 * (NSTAGE + 5);
constexpr uint32_t A_RDY = A_XBAR + 8 * 30;
constexpr int SMEM_BYTES = (A_XBAR + 8 * 32) - SBASE;
static_assert(SMEM_BYTES <= 232448, "smem");
constexpr int NUNITS = 784;

constexpr int NSCR = 56;
__device__ __align__(1024) uint4 g_wscratch[2 * NSCR * WBYTES / 16];
__device__ __align__(16) unsigned int g_counters[4];
constexpr unsigned int NPUB = NCTA * 8;

__device__ __forceinline__ void wgmma_n224(float (&d)[112], uint32_t a0, uint32_t a1, uint32_t a2, uint32_t a3, uint64_t descB) {
  asm volatile(
    "wgmma.mma_async.sync.aligned.m64n224k16.f32.bf16.bf16 {"
    "%0, %1, %2, %3, %4, %5, %6, %7, %8, %9, %10, %11, %12, %13, %14, %15, "
    "%16, %17, %18, %19, %20, %21, %22, %23, %24, %25, %26, %27, %28, %29, %30, %31, "
    "%32, %33, %34, %35, %36, %37, %38, %39, %40, %41, %42, %43, %44, %45, %46, %47, "
    "%48, %49, %50, %51, %52, %53, %54, %55, %56, %57, %58, %59, %60, %61, %62, %63, "
    "%64, %65, %66, %67, %68, %69, %70, %71, %72, %73, %74, %75, %76, %77, %78, %79, "
    "%80, %81, %82, %83, %84, %85, %86, %87, %88, %89, %90, %91, %92, %93, %94, %95, "
    "%96, %97, %98, %99, %100, %101, %102, %103, %104, %105, %106, %107, %108, %109, %110, %111}, "
    "{%112, %113, %114, %115}, %116, 1, 1, 1, 1;\n"
    : "+f"(d[0]), "+f"(d[1]), "+f"(d[2]), "+f"(d[3]), "+f"(d[4]), "+f"(d[5]), "+f"(d[6]), "+f"(d[7]),
      "+f"(d[8]), "+f"(d[9]), "+f"(d[10]), "+f"(d[11]), "+f"(d[12]), "+f"(d[13]), "+f"(d[14]), "+f"(d[15]),
      "+f"(d[16]), "+f"(d[17]), "+f"(d[18]), "+f"(d[19]), "+f"(d[20]), "+f"(d[21]), "+f"(d[22]), "+f"(d[23]),
      "+f"(d[24]), "+f"(d[25]), "+f"(d[26]), "+f"(d[27]), "+f"(d[28]), "+f"(d[29]), "+f"(d[30]), "+f"(d[31]),
      "+f"(d[32]), "+f"(d[33]), "+f"(d[34]), "+f"(d[35]), "+f"(d[36]), "+f"(d[37]), "+f"(d[38]), "+f"(d[39]),
      "+f"(d[40]), "+f"(d[41]), "+f"(d[42]), "+f"(d[43]), "+f"(d[44]), "+f"(d[45]), "+f"(d[46]), "+f"(d[47]),
      "+f"(d[48]), "+f"(d[49]), "+f"(d[50]), "+f"(d[51]), "+f"(d[52]), "+f"(d[53]), "+f"(d[54]), "+f"(d[55]),
      "+f"(d[56]), "+f"(d[57]), "+f"(d[58]), "+f"(d[59]), "+f"(d[60]), "+f"(d[61]), "+f"(d[62]), "+f"(d[63]),
      "+f"(d[64]), "+f"(d[65]), "+f"(d[66]), "+f"(d[67]), "+f"(d[68]), "+f"(d[69]), "+f"(d[70]), "+f"(d[71]),
      "+f"(d[72]), "+f"(d[73]), "+f"(d[74]), "+f"(d[75]), "+f"(d[76]), "+f"(d[77]), "+f"(d[78]), "+f"(d[79]),
      "+f"(d[80]), "+f"(d[81]), "+f"(d[82]), "+f"(d[83]), "+f"(d[84]), "+f"(d[85]), "+f"(d[86]), "+f"(d[87]),
      "+f"(d[88]), "+f"(d[89]), "+f"(d[90]), "+f"(d[91]), "+f"(d[92]), "+f"(d[93]), "+f"(d[94]), "+f"(d[95]),
      "+f"(d[96]), "+f"(d[97]), "+f"(d[98]), "+f"(d[99]), "+f"(d[100]), "+f"(d[101]), "+f"(d[102]), "+f"(d[103]),
      "+f"(d[104]), "+f"(d[105]), "+f"(d[106]), "+f"(d[107]), "+f"(d[108]), "+f"(d[109]), "+f"(d[110]), "+f"(d[111])
    : "r"(a0), "r"(a1), "r"(a2), "r"(a3), "l"(descB));
}
__device__ __forceinline__ void wgmma_n224_p(float (&d)[112], uint32_t a0, uint32_t a1, uint32_t a2, uint32_t a3, uint64_t descB, int scale_d) {
  asm volatile(
    "{\n.reg .pred p;\nsetp.ne.b32 p, %117, 0;\n"
    "wgmma.mma_async.sync.aligned.m64n224k16.f32.bf16.bf16 {"
    "%0, %1, %2, %3, %4, %5, %6, %7, %8, %9, %10, %11, %12, %13, %14, %15, "
    "%16, %17, %18, %19, %20, %21, %22, %23, %24, %25, %26, %27, %28, %29, %30, %31, "
    "%32, %33, %34, %35, %36, %37, %38, %39, %40, %41, %42, %43, %44, %45, %46, %47, "
    "%48, %49, %50, %51, %52, %53, %54, %55, %56, %57, %58, %59, %60, %61, %62, %63, "
    "%64, %65, %66, %67, %68, %69, %70, %71, %72, %73, %74, %75, %76, %77, %78, %79, "
    "%80, %81, %82, %83, %84, %85, %86, %87, %88, %89, %90, %91, %92, %93, %94, %95, "
    "%96, %97, %98, %99, %100, %101, %102, %103, %104, %105, %106, %107, %108, %109, %110, %111}, "
    "{%112, %113, %114, %115}, %116, p, 1, 1, 1;\n}\n"
    : "+f"(d[0]), "+f"(d[1]), "+f"(d[2]), "+f"(d[3]), "+f"(d[4]), "+f"(d[5]), "+f"(d[6]), "+f"(d[7]),
      "+f"(d[8]), "+f"(d[9]), "+f"(d[10]), "+f"(d[11]), "+f"(d[12]), "+f"(d[13]), "+f"(d[14]), "+f"(d[15]),
      "+f"(d[16]), "+f"(d[17]), "+f"(d[18]), "+f"(d[19]), "+f"(d[20]), "+f"(d[21]), "+f"(d[22]), "+f"(d[23]),
      "+f"(d[24]), "+f"(d[25]), "+f"(d[26]), "+f"(d[27]), "+f"(d[28]), "+f"(d[29]), "+f"(d[30]), "+f"(d[31]),
      "+f"(d[32]), "+f"(d[33]), "+f"(d[34]), "+f"(d[35]), "+f"(d[36]), "+f"(d[37]), "+f"(d[38]), "+f"(d[39]),
      "+f"(d[40]), "+f"(d[41]), "+f"(d[42]), "+f"(d[43]), "+f"(d[44]), "+f"(d[45]), "+f"(d[46]), "+f"(d[47]),
      "+f"(d[48]), "+f"(d[49]), "+f"(d[50]), "+f"(d[51]), "+f"(d[52]), "+f"(d[53]), "+f"(d[54]), "+f"(d[55]),
      "+f"(d[56]), "+f"(d[57]), "+f"(d[58]), "+f"(d[59]), "+f"(d[60]), "+f"(d[61]), "+f"(d[62]), "+f"(d[63]),
      "+f"(d[64]), "+f"(d[65]), "+f"(d[66]), "+f"(d[67]), "+f"(d[68]), "+f"(d[69]), "+f"(d[70]), "+f"(d[71]),
      "+f"(d[72]), "+f"(d[73]), "+f"(d[74]), "+f"(d[75]), "+f"(d[76]), "+f"(d[77]), "+f"(d[78]), "+f"(d[79]),
      "+f"(d[80]), "+f"(d[81]), "+f"(d[82]), "+f"(d[83]), "+f"(d[84]), "+f"(d[85]), "+f"(d[86]), "+f"(d[87]),
      "+f"(d[88]), "+f"(d[89]), "+f"(d[90]), "+f"(d[91]), "+f"(d[92]), "+f"(d[93]), "+f"(d[94]), "+f"(d[95]),
      "+f"(d[96]), "+f"(d[97]), "+f"(d[98]), "+f"(d[99]), "+f"(d[100]), "+f"(d[101]), "+f"(d[102]), "+f"(d[103]),
      "+f"(d[104]), "+f"(d[105]), "+f"(d[106]), "+f"(d[107]), "+f"(d[108]), "+f"(d[109]), "+f"(d[110]), "+f"(d[111])
    : "r"(a0), "r"(a1), "r"(a2), "r"(a3), "l"(descB), "r"(scale_d));
}


#define ELECT_P "{\n.reg .pred p;\nelect.sync _|p, 0xffffffff;\n"
__device__ __forceinline__ void mbar_init(uint32_t b, int c) {
  asm volatile("mbarrier.init.shared::cta.b64 [%0], %1;" ::"r"(b), "r"(c) : "memory");
}
__device__ __forceinline__ void mbar_arrive(uint32_t b) {
  asm volatile(ELECT_P "@p mbarrier.arrive.shared::cta.b64 _, [%0];\n}\n" ::"r"(b) : "memory");
}
__device__ __forceinline__ uint32_t mbar_try(uint32_t b) {
  uint32_t ok;
  asm volatile("{\n.reg .pred p;\nmbarrier.try_wait.parity.shared::cta.b64 p, [%1], 0;\nselp.u32 %0, 1, 0, p;\n}\n"
               : "=r"(ok) : "r"(b) : "memory");
  return ok;
}
__device__ __forceinline__ void mbar_wait(uint32_t b) {
  uint32_t n = 0;
  while (!__all_sync(0xffffffffu, mbar_try(b)) && ++n < (1u << 20)) {}
}
__device__ __forceinline__ void tma_load_4d(uint32_t dst, const CUtensorMap* m, int c0, int c1, int c2, int c3, uint32_t bar, int bytes) {
  asm volatile(ELECT_P "@p mbarrier.arrive.expect_tx.shared::cta.b64 _, [%6], %7;\n"
               "@p cp.async.bulk.tensor.4d.shared::cluster.global.mbarrier::complete_tx::bytes.L2::cache_hint [%0], [%1, {%2, %3, %4, %5}], [%6], %8;\n}\n"
               ::"r"(dst), "l"(m), "r"(c0), "r"(c1), "r"(c2), "r"(c3), "r"(bar), "r"(bytes), "l"(EVICT_FIRST) : "memory");
}
__device__ __forceinline__ void tma_prefetch_4d(const CUtensorMap* m, int c0, int c1, int c2, int c3) {
  asm volatile(ELECT_P "@p cp.async.bulk.prefetch.tensor.4d.L2.global.L2::cache_hint [%0, {%1, %2, %3, %4}], %5;\n}\n"
               ::"l"(m), "r"(c0), "r"(c1), "r"(c2), "r"(c3), "l"(EVICT_FIRST) : "memory");
}
__device__ __forceinline__ void bulk_load(uint32_t dst, const void* src, int bytes, uint32_t bar) {
  asm volatile(ELECT_P "@p mbarrier.arrive.expect_tx.shared::cta.b64 _, [%3], %2;\n"
               "@p cp.async.bulk.shared::cluster.global.mbarrier::complete_tx::bytes [%0], [%1], %2, [%3];\n}\n"
               ::"r"(dst), "l"(src), "r"(bytes), "r"(bar) : "memory");
}
__device__ __forceinline__ void bulk_store(void* dst, uint32_t src, int bytes) {
  asm volatile(ELECT_P "@p cp.async.bulk.global.shared::cta.bulk_group [%0], [%1], %2;\n}\n"
               ::"l"(dst), "r"(src), "r"(bytes) : "memory");
}
__device__ __forceinline__ void tma_store_5d(const CUtensorMap* m, uint32_t src, int c0, int c1, int c2, int c3, int c4) {
  asm volatile(ELECT_P "@p cp.async.bulk.tensor.5d.global.shared::cta.bulk_group.L2::cache_hint [%0, {%2, %3, %4, %5, %6}], [%1], %7;\n}\n"
               "cp.async.bulk.commit_group;\n"
               ::"l"(m), "r"(src), "r"(c0), "r"(c1), "r"(c2), "r"(c3), "r"(c4), "l"(EVICT_FIRST) : "memory");
}
#define FENCE_ASYNC_SMEM() asm volatile("fence.proxy.async.shared::cta;" ::: "memory")
__device__ __forceinline__ void ldsm4(uint32_t (&r)[4], uint32_t a) {
  asm volatile("ldmatrix.sync.aligned.m8n8.x4.shared.b16 {%0,%1,%2,%3}, [%4];"
               : "=r"(r[0]), "=r"(r[1]), "=r"(r[2]), "=r"(r[3]) : "r"(a) : "memory");
}
__device__ __forceinline__ void ldsm4_if(uint32_t (&r)[4], uint32_t a, uint32_t pred) {
  asm volatile("{\n.reg .pred p;\nsetp.ne.u32 p, %5, 0;\n@p ldmatrix.sync.aligned.m8n8.x4.shared.b16 {%0,%1,%2,%3}, [%4];\n}\n"
               : "+r"(r[0]), "+r"(r[1]), "+r"(r[2]), "+r"(r[3]) : "r"(a), "r"(pred) : "memory");
}
__device__ __forceinline__ void stsm4(uint32_t a, uint32_t r0, uint32_t r1, uint32_t r2, uint32_t r3) {
  asm volatile("stmatrix.sync.aligned.m8n8.x4.shared.b16 [%0], {%1,%2,%3,%4};" ::"r"(a), "r"(r0), "r"(r1), "r"(r2), "r"(r3) : "memory");
}
__device__ __forceinline__ void cp_async16(uint32_t dst, const void* src) {
  asm volatile("cp.async.cg.shared.global [%0], [%1], 16;" ::"r"(dst), "l"(src) : "memory");
}
__device__ __forceinline__ uint32_t lds32(uint32_t a) {
  uint32_t v; asm volatile("ld.shared.u32 %0, [%1];" : "=r"(v) : "r"(a) : "memory"); return v;
}
__device__ __forceinline__ float lds_bf16(uint32_t a) {
  uint16_t v; asm volatile("ld.shared.u16 %0, [%1];" : "=h"(v) : "r"(a) : "memory"); return __uint_as_float((uint32_t)v << 16);
}
__device__ __forceinline__ void sts128(uint32_t a, uint32_t r0, uint32_t r1, uint32_t r2, uint32_t r3) {
  asm volatile("st.shared.v4.u32 [%0], {%1,%2,%3,%4};" ::"r"(a), "r"(r0), "r"(r1), "r"(r2), "r"(r3) : "memory");
}
__device__ __forceinline__ void lds128(uint32_t* r, uint32_t a) {
  asm volatile("ld.shared.v4.u32 {%0,%1,%2,%3}, [%4];" : "=r"(r[0]), "=r"(r[1]), "=r"(r[2]), "=r"(r[3]) : "r"(a) : "memory");
}
__device__ __forceinline__ uint32_t hfma2(uint32_t a, uint32_t b, uint32_t c) {
  uint32_t d; asm volatile("fma.rn.bf16x2 %0, %1, %2, %3;" : "=r"(d) : "r"(a), "r"(b), "r"(c)); return d;
}
__device__ __forceinline__ uint32_t lane_id() { uint32_t l; asm volatile("mov.u32 %0, %%laneid;" : "=r"(l)); return l; }
__device__ __forceinline__ float bf_lo(uint32_t v) { return __uint_as_float(v << 16); }
__device__ __forceinline__ float bf_hi(uint32_t v) { return __uint_as_float(v & 0xffff0000u); }
__device__ __forceinline__ uint32_t hsub2(uint32_t a, uint32_t b) {
  uint32_t d; asm volatile("sub.rn.bf16x2 %0, %1, %2;" : "=r"(d) : "r"(a), "r"(b)); return d;
}
__device__ __forceinline__ uint32_t hadd2(uint32_t a, uint32_t b) {
  uint32_t d; asm volatile("add.rn.bf16x2 %0, %1, %2;" : "=r"(d) : "r"(a), "r"(b)); return d;
}
__device__ __forceinline__ uint32_t pack_bf16(float lo, float hi) {
  uint32_t d; asm("cvt.rn.bf16x2.f32 %0, %1, %2;" : "=r"(d) : "f"(hi), "f"(lo)); return d;
}
__device__ __forceinline__ float sqrt_fast(float v) { float r; asm("sqrt.approx.f32 %0, %1;" : "=f"(r) : "f"(v)); return r; }
__device__ __forceinline__ float round_bf16(float v) { return bf_hi(pack_bf16(0.f, v)); }
__device__ __forceinline__ float silu_half(float h) {
  float t; asm("tanh.approx.f32 %0, %1;" : "=f"(t) : "f"(h)); return fmaf(h, t, h);
}
#define WG_FENCE() asm volatile("wgmma.fence.sync.aligned;" ::: "memory")
#define WG_COMMIT() asm volatile("wgmma.commit_group.sync.aligned;" ::: "memory")
#define STR2(x) #x
#define STR(x) STR2(x)
#define WG_WAIT0() asm volatile("wgmma.wait_group.sync.aligned 0; // L" STR(__LINE__) ::: "memory")
#define WG_WAIT1() asm volatile("wgmma.wait_group.sync.aligned 1;" ::: "memory")

constexpr uint32_t WD0 = (A_W >> 4) | (128u << 16);
__device__ __forceinline__ uint64_t wdesc(uint32_t wd) { return ((uint64_t)(32u | (2u << 30)) << 32) | wd; }
__device__ __forceinline__ uint64_t wdesc_raw(uint32_t wd) { return ((uint64_t)(64u | (1u << 30)) << 32) | (wd + (128u << 16)); }

struct Params {
  const __nv_bfloat16* x;
  const __nv_bfloat16* w;
  const __nv_bfloat16* mean;
  const __nv_bfloat16* var;
  const __nv_bfloat16* g;
  const __nv_bfloat16* b;
  char* scratch;
  unsigned int* counters;
  uint32_t need;
  uint32_t zero_;
  int seven_;
};

struct Maps { CUtensorMap x, o, w[2]; };

struct Ctx {
  const CUtensorMap* mx; const CUtensorMap* mw; const CUtensorMap* mo;
  const char* scratch;
  int half, b0, warp;
};

__device__ __forceinline__ void w_load_raw(const Ctx& c, uint32_t wa, int t, uint32_t bar) {
  asm volatile(ELECT_P "@p mbarrier.arrive.expect_tx.shared::cta.b64 _, [%5], %6;\n"
               "@p cp.async.bulk.tensor.3d.shared::cluster.global.mbarrier::complete_tx::bytes [%0], [%1, {%7, %3, %4}], [%5];\n"
               "@p cp.async.bulk.tensor.3d.shared::cluster.global.mbarrier::complete_tx::bytes [%0+12288], [%2, {%8, %3, %9}], [%5];\n}\n"
               ::"r"(wa), "l"(c.mw), "l"(c.mw + 1), "r"(32 * t), "r"(4 * c.half), "r"(bar), "r"(WSLOT), "r"(0), "r"(192), "r"(c.half)
               : "memory");
}
__device__ __forceinline__ void w_load_scratch(const Ctx& c, uint32_t wa, int t, uint32_t bar) {
  bulk_load(wa, c.scratch + t * WBYTES, WBYTES, bar);
}
__device__ __forceinline__ void out_store(const Ctx& c, uint32_t src, int box, int batch, int parity) {
  tma_store_5d(c.mo, src, box < 3 ? 64 * box + 32 * c.half : 192, batch, 2 * c.warp, parity, box < 3 ? 7 * c.half : c.half);
}
__device__ __forceinline__ unsigned int ld_ready(const unsigned int* ready) {
  unsigned int v;
  asm volatile("ld.relaxed.gpu.global.u32 %0, [%1];" : "=r"(v) : "l"(ready) : "memory");
  return v;
}
__device__ __forceinline__ uint32_t xnext(uint32_t s) { return s == NX - 1 ? 0 : s + 1; }
__device__ __forceinline__ uint32_t xprev(uint32_t s) { return s == 0 ? NX - 1 : s - 1; }
__device__ __forceinline__ void x_load(const Ctx& c, uint32_t slot, int chunk, int pass, int odd) {
  tma_load_4d(A_X + slot * XSLOT, c.mx, 64 * chunk, c.b0 + 8 * pass, 0, odd, A_XBAR + 8 * (15 * pass + 7 * (1 - odd) + chunk),
              XSLOT);
}

#define GRP(j) (((j) + 12) % 14)
template <int I> struct IC { static constexpr int v = I; };
template <int N, int I = 0, class F>
__device__ __forceinline__ void static_for(F&& f) {
  if constexpr (I < N) { f(IC<I>{}); static_for<N, I + 1>(f); }
}
__device__ __forceinline__ uint32_t silu2(uint32_t h) { return pack_bf16(silu_half(bf_lo(h)), silu_half(bf_hi(h))); }

template <int W, class F>
__device__ __forceinline__ void pack_bn(uint32_t (&pk)[56], const float (&acc)[112], uint32_t lane_par, uint32_t zero_, F&& pre) {
  uint32_t par[14][4];
#pragma unroll
  for (int g = 0; g < W; g++) lds128(par[g], lane_par + g * 64);
#pragma unroll
  for (int g = 0; g < 14; g++) {
    pre(g);
#pragma unroll
    for (int i = 0; i < 4; i++) {
      uint32_t y;
      asm volatile("cvt.rn.bf16x2.f32 %0, %2, %1;" : "=r"(y) : "f"(acc[8 * g + 2 * i]), "f"(acc[8 * g + 2 * i + 1]));
      pk[4 * g + i] = hfma2(y, par[g][i >> 1], par[g][2 + (i >> 1)]);
    }
    if (g + W < 14) lds128(par[g + W], (lane_par | (pk[4 * g + 3] & zero_)) + (g + W) * 64);
  }
}

constexpr uint32_t WDSTEP = WSLOT / 16;
__device__ __forceinline__ uint32_t wd_next(uint32_t wd) { return wd == WD0 + (NW - 1) * WDSTEP ? WD0 : wd + WDSTEP; }
__device__ __forceinline__ uint32_t wd_refill_addr(uint32_t wd) {
  return ((wd < WD0 + 2 * WDSTEP ? wd + 3 * WDSTEP : wd - 2 * WDSTEP) & 0xffffu) << 4;
}

__global__ void __launch_bounds__(256, 1)
conv_bn_silu_kernel(const __grid_constant__ Maps maps, const Params prm) {
  extern __shared__ __align__(1024) char smem_raw[];
  const int tid = threadIdx.x;
  Ctx c;
  c.mx = &maps.x; c.mw = maps.w; c.mo = &maps.o;
  c.half = blockIdx.x & 1;
  c.b0 = (blockIdx.x >> 1) * 16;
  c.warp = __shfl_sync(0xffffffff, tid >> 5, 0);
#define zero prm.zero_
#define seven prm.seven_
  if ((tid >> 6) == 2) {
    asm volatile("prefetch.global.L2 [%0];" ::"l"(prm.x + ((c.b0 + 4 * c.half + (tid & 3)) * 32 + ((tid >> 2) & 15) * 2 + 1) * CH));
  }
  if ((uint32_t)__cvta_generic_to_shared(smem_raw) != SBASE) return;
  if (c.warp == 0) {
#pragma unroll 1
    for (int i = 0; i < 5; i++) {
      mbar_init(A_WBAR + 16 * i, 1);
      mbar_init(A_XBAR + 8 * i, 1);
      __syncwarp();
      if (!(i & 1)) x_load(c, i >> 1, i >> 1, 0, 1);
      w_load_raw(c, A_W + i * WSLOT, i, A_WBAR + 16 * i);
    }
#pragma unroll
    for (int i = 5; i < 8; i++) mbar_init(A_XBAR + 8 * i, 1);
#pragma unroll
    for (int i = -1; i < 5; i++) mbar_init(A_WBAR + 16 * i + 8, 8);
  }
  const int unit = blockIdx.x * 7 + c.warp - 1;
  const bool has_unit = c.warp != 0 && unit < NUNITS;
  const int ug = unit / 56, uc = unit - ug * 56;
  constexpr uint32_t A_SET = A_X + 8 * XSLOT;
  uint32_t pk[56];
  uint32_t epoch = 0, ready = 0;
  if (c.warp == 0) {
    if (tid < 28) {
      cp_async16(A_SET + tid * 16, prm.var + c.half * 224 + tid * 8);
      cp_async16(A_SET + 448 + tid * 16, prm.g + c.half * 224 + tid * 8);
      cp_async16(A_SET + 896 + tid * 16, prm.mean + c.half * 224 + tid * 8);
      cp_async16(A_SET + 1344 + tid * 16, prm.b + c.half * 224 + tid * 8);
    } else if (tid == 28) {
      cp_async16(A_SET + 1792, prm.counters);
    }
    __syncwarp();
  } else {
    if (has_unit) {
      const uint4* wp = (const uint4*)(prm.w + (uc * 8 + ((tid >> 2) & 7)) * CH + ug * 32) + (tid & 3);
#pragma unroll
      for (int k = 0; k < 3; k++) cp_async16(A_SET + c.warp * 2048 + k * 512 + (tid & 31) * 16, wp + k * (CH * CH / 8));
    }
    const uint32_t bar = A_WBAR + 16 * (c.warp * 16 - 11);
#pragma unroll
    for (int i = 0; i < 16; i++) { mbar_init(bar + 16 * i, 1); mbar_init(bar + 16 * i + 8, 8); }
#pragma unroll
    for (int i = 0; i < 4; i++) if (c.warp > 1) mbar_init(A_XBAR + 8 * (c.warp * 4 + i), 1);
    __syncwarp();
    if (c.warp == 7) mbar_arrive(A_WBAR + 16 * NSTAGE);
  }
  __syncthreads();
  c.scratch = prm.scratch + c.half * (NSCR * WBYTES);
  asm volatile("" : "+l"(c.scratch));

  auto transform_weights = [&]() {
    asm volatile("cp.async.wait_all;" ::: "memory");
    if (has_unit) {
      const uint32_t l = lane_id();
      const uint32_t sb = A_SET + c.warp * 2048, sa = sb + (l >> 2) * 64 + (((l & 3) ^ ((l >> 3) & 3)) << 4);
      uint32_t g0[4], g1[4], g2[4], o1[4], o2[4], o3[4];
      lds128(g0, sb + l * 16);
      lds128(g1, sb + 512 + l * 16);
      lds128(g2, sb + 1024 + l * 16);
#pragma unroll
      for (int k = 0; k < 4; k++) {
        const float sl = bf_lo(g0[k]) + bf_lo(g2[k]), sh = bf_hi(g0[k]) + bf_hi(g2[k]);
        o1[k] = pack_bf16(sl + bf_lo(g1[k]), sh + bf_hi(g1[k]));
        o2[k] = pack_bf16(sl - bf_lo(g1[k]), sh - bf_hi(g1[k]));
        o3[k] = pack_bf16(-2.f * bf_lo(g2[k]), -2.f * bf_hi(g2[k]));
      }
      __syncwarp();
      sts128(sa, o1[0], o1[1], o1[2], o1[3]);
      sts128(sa + 512, o2[0], o2[1], o2[2], o2[3]);
      sts128(sa + 1024, o3[0], o3[1], o3[2], o3[3]);
      sts128(sa + 1536, g0[0], g0[1], g0[2], g0[3]);
    }
    __syncwarp();
    FENCE_ASYNC_SMEM();
    __syncwarp();
    if (has_unit) {
      const uint32_t sb = A_SET + c.warp * 2048;
      const int h = ug >= 7 ? 1 : 0;
      char* base = prm.scratch + h * (NSCR * WBYTES) + (ug == 7 ? 6 : ug - 8 * h) * 2048;
      char* pT = base + (14 + (uc >> 1)) * WBYTES + (uc & 1) * 512;
      char* pE = base + (uc >> 2) * WBYTES + (uc & 3) * 512;
      bulk_store(pT, sb, 512);
      bulk_store(pT + 1024, sb + 512, 512);
      bulk_store(pE + 42 * WBYTES, sb + 1024, 512);
      bulk_store(pE, sb + 1536, 512);
      asm volatile("cp.async.bulk.commit_group;" ::: "memory");
    }
  };
  auto setup_params = [&]() {
    if (c.warp != 0) {
      const int pt = c.warp * 32 + lane_id() - 32;
      const uint32_t src = A_SET + 2 * (c.half ? (pt < 192 ? pt + 32 : pt - 192) : pt);
      const float sd = round_bf16(sqrt_fast(round_bf16(lds_bf16(src) + 1e-5f)));
      const float sc = round_bf16(lds_bf16(src + 448) * round_bf16(__fdividef(1.f, sd)));
      const float sh = fmaf(-lds_bf16(src + 896), sc, lds_bf16(src + 1344));
      const uint32_t word = pack_bf16(0.25f * sc, 0.5f * sh);
      const uint32_t pa = A_PAR + (pt >> 4) * 64 + ((pt >> 1) & 3) * 16 + ((pt >> 3) & 1) * 4 + (pt & 1) * 2;
      asm volatile("st.shared.u16 [%0], %1;" ::"r"(pa), "h"((uint16_t)word) : "memory");
      asm volatile("st.shared.u16 [%0], %1;" ::"r"(pa + 8), "h"((uint16_t)(word >> 16)) : "memory");
    }
    __syncwarp();
  };

  float accA[112], accB[112];
#pragma unroll
  for (int i = 0; i < 112; i++) asm volatile("" : "=f"(accA[i]));
  uint32_t wd = WD0;
  uint32_t wb = A_WBAR;
  uint32_t lane_e, lane_stg, lane_par;
  auto edge_lanes = [&]() {
    const uint32_t l = lane_id(), mi = l >> 3, row = l & 7;
    lane_e = A_X + 2 * c.warp * 1024 + row * 128 + ((mi ^ row) << 4);
    lane_stg = (mi & 1) * 1024 + row * 128 + (((mi >> 1) ^ row) << 4);
    lane_par = A_PAR + (l & 3) * 16;
  };
  auto t_lane = [&]() { const uint32_t m = lane_id() & 16; return (lane_e ^ (m * 2)) + m * 64; };
  edge_lanes();
  uint32_t q0[4] = {0, 0, 0, 0}, q1[4], q2[4], f[8];
  auto frags = [&]() {
#pragma unroll
    for (int i = 0; i < 4; i++) { f[2 * i] = hsub2(q0[i], q1[i]); f[2 * i + 1] = hsub2(q1[i], q2[i]); }
  };
  uint32_t ae, ao;

  {
    uint32_t xa = lane_e;
    auto loads = [&](uint32_t ad) {
      ldsm4_if(q0, ad - 1024, c.warp);
      ldsm4(q1, ad);
      ldsm4(q2, ad + 1024);
    };
    if (c.warp != 0) transform_weights();
    mbar_wait(A_XBAR);
    loads(xa);
    frags();
    loads(xa ^ 64);
    mbar_wait(A_WBAR);
    if (seven) {
#pragma unroll 1
    for (int ch = 0; ch < 7; ch++) {
      static_for<2>([&](auto H) {
        constexpr int h = H.v;
        const int j = 2 * ch + h;
        const uint32_t eb = wb + 16 * h - 8, fb = wb + 16 * h + 16, xnb = A_XBAR + 8 * ch + 8;
        WG_FENCE();
        if constexpr (h == 0) wgmma_n224_p(accA, f[0], f[1], f[2], f[3], wdesc_raw(wd), ch);
        else wgmma_n224(accA, f[0], f[1], f[2], f[3], wdesc_raw(wd));
        wgmma_n224(accA, f[4], f[5], f[6], f[7], wdesc_raw(wd + 128));
        WG_COMMIT();
        WG_WAIT1();
        mbar_arrive(eb);
        if (__builtin_expect((c.warp & 3) == 1, 0)) {
          if (c.warp == (h ? 5 : 1)) {
            if (j < 11) {
              if (j >= 2) w_load_raw(c, wd_refill_addr(wd), j + 3, wb + 16 * h + 48);
              if (h == 1 && j == J_RDY) { if (lane_id() == 0) cp_async16(A_RDY, prm.counters); __syncwarp(); }
            } else {
              asm volatile("fence.proxy.async.global;" ::: "memory");
              w_load_scratch(c, wd_refill_addr(wd), j + 3, wb + 16 * h + 48);
            }
          } else if (h == 0) {
            if (ch < 6) x_load(c, ch + 3, ch < 4 ? ch + 3 : ch - 4, 0, ch < 4);
            else tma_prefetch_4d(c.mx, 128, c.b0, 0, 0);
            if (ch == 5) {
              asm volatile("cp.async.wait_all;" ::: "memory");
              __syncwarp();
              ready = lds32(A_RDY);
              uint32_t n = 0;
#pragma unroll 1
              while (!__all_sync(0xffffffffu, ready - epoch >= prm.need) && ++n < (1u << 22)) ready = ld_ready(prm.counters);
            }
          }
        }
        uint32_t ok = mbar_try(fb) & mbar_try(eb);
        if constexpr (h == 0) ok &= mbar_try(xnb);
        if (h == 1 && c.warp == 0) asm volatile("cp.async.wait_all;" ::: "memory");
        if ((J_PUB & 1) == h && __builtin_expect(j == J_PUB, 0)) {
          setup_params();
          asm volatile("cp.async.bulk.wait_group 0;" ::: "memory");
          epoch = lds32(A_SET + 1792) & ~(NPUB - 1);
          asm volatile(ELECT_P "@p red.relaxed.gpu.global.add.u32 [%0], 1;\n}\n" ::"l"(prm.counters) : "memory");
        }
        frags();
        wd = wd_next(wd);
        if (__builtin_expect(!__all_sync(0xffffffffu, ok), 0)) {
          uint32_t n = 0;
          do {
            ok = mbar_try(fb) & mbar_try(eb);
            if constexpr (h == 0) ok &= mbar_try(xnb);
          } while (!__all_sync(0xffffffffu, ok) && ++n < (1u << 20));
        }
        if constexpr (h == 0) xa += XSLOT;
        loads(h ? xa ^ 64 : xa);
      });
      wb += 32;
    }
    WG_WAIT0();
    }
    ao = t_lane();
    ae = ao + 7 * XSLOT;
    ldsm4(q1, ae);
    ldsm4(q2, ao);
    WG_WAIT0();
  }

#pragma unroll 1
  for (int e = 1; e < 4; e++) {
    const int p3 = e & 1, pass = e >> 1;
    uint32_t xs;
    WG_WAIT0();
    if (p3) {
      uint32_t xo = 6 * pass;
      uint32_t xb = A_XBAR + 8 * (15 * pass + 7);
      xs = 7 - 3 * pass;
#pragma unroll
      for (int i = 0; i < 112; i++) asm volatile("mov.b32 %0, %1;" : "=f"(accB[i]) : "f"(accA[i]));
      if (seven)
#pragma unroll 1
      for (int kc = 0; kc < 7; kc++) {
        static_for<4>([&](auto KS) {
          constexpr int ks = KS.v;
          const uint32_t eb = wb + 16 * ks - 8, fb = wb + 16 * ks + 16;
          {
            const uint32_t a0 = hadd2(q1[0], q2[0]), a1 = hadd2(q1[2], q2[2]), a2 = hadd2(q1[1], q2[1]), a3 = hadd2(q1[3], q2[3]);
            WG_FENCE();
            wgmma_n224(accA, a0, a1, a2, a3, wdesc(wd));
            WG_COMMIT();
            if constexpr (ks == 0) asm volatile("cp.async.bulk.wait_group.read 0;" ::: "memory");
            mbar_arrive(eb);
            if (__builtin_expect(c.warp == ((ks & 1) ? 5 : 1), 0)) {
              w_load_scratch(c, wd_refill_addr(wd), 4 * kc + ks + 17, wb + 16 * ks + 48);
              if (ks == 0 && kc && kc < 6) x_load(c, xprev(xo), kc + 1, pass, 0);
              if (ks == 1 && kc == 0 && pass == 1) x_load(c, 5, 1, 1, 0);
              if (ks == 3 && kc < 4) tma_prefetch_4d(c.mx, 64 * (kc + 3), c.b0 + 8 * pass, 0, 0);
            }
            if constexpr (ks == 3) {
              ae += xs == NX - 1 ? -(NX - 1) * XSLOT : XSLOT;
              ao += xo == NX - 1 ? -(NX - 1) * XSLOT : XSLOT;
              xo = xnext(xo);
              xs = xnext(xs);
              const uint32_t odd_grp = kc == 6 ? ~ao & 1024 : 0;
              ao = (ao - odd_grp) ^ (odd_grp >> 5);
              ae = kc == 6 ? ao + 1024 : ae;
              xb += kc < 6 ? 8 : 0;
              mbar_wait(xb);
            }
            WG_WAIT0();
          }
          {
            const uint32_t a0 = hsub2(q2[0], q1[0]), a1 = hsub2(q2[2], q1[2]), a2 = hsub2(q2[1], q1[1]), a3 = hsub2(q2[3], q1[3]);
            WG_FENCE();
            wgmma_n224(accB, a0, a1, a2, a3, wdesc(wd + 64));
            WG_COMMIT();
            wd = wd_next(wd);
            uint32_t ok = mbar_try(fb) & mbar_try(eb);
            ldsm4(q1, ae ^ (((ks + 1) & 3) << 5));
            ldsm4(q2, ao ^ (((ks + 1) & 3) << 5));
            if (__builtin_expect(!__all_sync(0xffffffffu, ok), 0)) {
              uint32_t n = 0;
              do {
                ok = mbar_try(fb) & mbar_try(eb);
              } while (!__all_sync(0xffffffffu, ok) && ++n < (1u << 20));
            }
            WG_WAIT0();
          }
        });
        wb += 16 * 4;
      }
      xs = 7 - 3 * pass;
      ae = ao = 0;
      lane_par = A_PAR + (lane_id() & 3) * 16;
      pack_bn<T2W>(pk, accB, lane_par, zero, [&](int g) {
#pragma unroll
        for (int i = 8 * g; i < 8 * g + 8; i++)
          asm volatile("sub.f32 %0, %0, %1;\nfma.rn.f32 %1, %1, 0f40000000, %0;\n" : "+f"(accA[i]), "+f"(accB[i]));
        if (g == 10) {
          edge_lanes();
#pragma unroll
          for (int i = 0; i < 4; i++) { q0[i] = q2[i]; q2[i] = 0; }
          ldsm4_if(q2, (lane_e | (pk[4 * 9] & zero)) + xs * XSLOT + 2048, c.warp ^ 7);
        }
      });
    } else {
      xs = 6;
      pack_bn<BW>(pk, accA, lane_par, zero, [](int) {});
    }

    if (seven) {
      const uint32_t xb = A_XBAR + 8 * 15;
      const uint32_t stg = A_X + (e == 3 ? 2 : 5) * XSLOT + c.warp * 2048;
      const int ob = c.b0 + (e == 3 ? 8 : 0);
      const uint32_t ld0 = p3 | c.warp, ld2 = (p3 ^ 1) | (c.warp ^ 7);
      const char* wsrc = c.scratch + p3 * (42 * WBYTES);
      const uint32_t lane_m = lane_e + p3 * 1024;
      const uint32_t xpb = p3 ? A_XBAR : xb;
      auto loads = [&](uint32_t ad) {
        ldsm4_if(q0, ad - 1024, ld0);
        ldsm4(q1, ad);
        ldsm4_if(q2, ad + 1024, ld2);
      };
      uint32_t xa = lane_m + xs * XSLOT;
      frags();
      loads(xa ^ 64);

      static_for<14>([&](auto J) {
        constexpr int j = J.v, h = j & 1, ch = j >> 1;
        const uint32_t eb = wb + 16 * j - 8, fb = wb + 16 * j + 16;
        WG_FENCE();
        if constexpr (j == 0) wgmma_n224_p(accA, f[0], f[1], f[2], f[3], wdesc(wd), p3);
        else wgmma_n224(accA, f[0], f[1], f[2], f[3], wdesc(wd));
        wgmma_n224(accA, f[4], f[5], f[6], f[7], wdesc(wd + 64));
        WG_COMMIT();
        WG_WAIT1();
        mbar_arrive(eb);
        if (__builtin_expect(c.warp == (h ? 5 : 1), 0)) {
          if (j < 11 || e != 3)
            bulk_load(wd_refill_addr(wd), (j >= 11 && p3 ? c.scratch - 14 * WBYTES : wsrc) + (j + 3) * WBYTES, WBYTES, wb + 16 * j + 48);
          if (h == 1 && e == 1) x_load(c, (6 + ch) % 9, ch, 1, 1);
          if (j == 0 && e == 2) x_load(c, 4, 0, 1, 0);
          if ((j == 10 || j == 12) && e == 2) tma_prefetch_4d(c.mx, j == 10 ? 64 : 128, c.b0 + 8, 0, 0);
        }
        wd = wd_next(wd);
        if constexpr (h == 0) { xs = xnext(xs); xa = lane_m + xs * XSLOT; }
        constexpr bool probe_x = (h == 0 && ch < 6) || j == 13;
        const uint32_t xnb = j < 13 ? xpb + 8 * ch + 8 : (p3 ? xb : xb + 56);
        auto stage_out = [&](auto JJ) {
          constexpr int g = GRP(JJ.v);
          stsm4(stg + (lane_stg ^ ((g & 3) << 5)), pk[4 * g], pk[4 * g + 1], pk[4 * g + 2], pk[4 * g + 3]);
        };
        auto pin = [&](auto JJ) {
          constexpr int g = GRP(JJ.v);
          asm volatile("{\n.reg .pred p;\nsetp.ne.u32 p, %4, 0;\n@p st.shared.v4.u32 [%4], {%0,%1,%2,%3};\n}\n"
                       ::"r"(pk[4 * g]), "r"(pk[4 * g + 1]), "r"(pk[4 * g + 2]), "r"(pk[4 * g + 3]), "r"(zero));
        };
        auto store = [&]() {
          __syncwarp();
          out_store(c, stg, GRP(j - 1) >> 2, ob, p3 ^ 1);
        };
        constexpr int r = (j + 2) & 3;
        uint32_t ok = mbar_try(fb);
        if constexpr (probe_x) ok &= mbar_try(xnb);
        ok &= mbar_try(eb);
        if constexpr (r == 0 || j == 13) FENCE_ASYNC_SMEM();
        if constexpr (j < 13) {
#pragma unroll
          for (int i = 0; i < 4; i++) pk[4 * GRP(j) + i] = silu2(pk[4 * GRP(j) + i]);
        }
        if constexpr (j == 12) {
#pragma unroll
          for (int i = 0; i < 4; i++) pk[4 * GRP(13) + i] = silu2(pk[4 * GRP(13) + i]);
        }
        constexpr int first = 2;
        if constexpr (r < first) {
          pin(IC<j>{});
          if constexpr (r == 0) store();
        } else {
          if constexpr (r == first || j == 0) {
            asm volatile("cp.async.bulk.wait_group.read 0;" ::: "memory");
            __syncwarp();
            if constexpr (j > 0) static_for<first>([&](auto I) { stage_out(IC<j - 1 - I.v>{}); });
          }
          if constexpr (j < 13) stage_out(IC<j>{});
          if constexpr (j == 12) stage_out(IC<13>{});
        }
        if constexpr (j < 13) frags();
        if (__builtin_expect(!__all_sync(0xffffffffu, ok), 0)) {
          uint32_t n = 0;
          do {
            ok = mbar_try(fb) & mbar_try(eb);
            if constexpr (probe_x) ok &= mbar_try(xnb);
          } while (!__all_sync(0xffffffffu, ok) && ++n < (1u << 20));
        }
        if constexpr (j < 12) loads(h ? xa ^ 64 : xa);
        if constexpr (j == 13) {
          ao = t_lane() + 6 * XSLOT;
          ae = ao - 2 * XSLOT;
          const uint32_t a1 = p3 ? lane_e + 6 * XSLOT : ae, a2 = p3 ? a1 + 1024 : ao;
#pragma unroll
          for (int i = 0; i < 4; i++) q0[i] = 0;
          ldsm4_if(q0, a1 - 1024, c.warp);
          ldsm4(q1, a1);
          ldsm4(q2, a2);
          __syncwarp();
          out_store(c, stg, 2, ob, p3 ^ 1);
        }
        if constexpr (j == 13) WG_WAIT0();
      });
      wb += 16 * 14;
    }
  }
#pragma unroll
  for (int j = 0; j < TAILW; j++) lds128(pk + 4 * j, lane_par + j * 64);
  WG_WAIT0();
  static_for<14>([&](auto J) {
    constexpr int j = J.v;
    const uint32_t* pr = pk + 4 * j;
    uint32_t p[4];
#pragma unroll
    for (int i = 0; i < 4; i++) {
      const uint32_t sp = pr[i >> 1], tp = pr[2 + (i >> 1)];
      const float h0 = accA[8 * j + 2 * i], h1 = accA[8 * j + 2 * i + 1];
      p[i] = pack_bf16(silu_half(fmaf(h0, bf_lo(sp), bf_lo(tp))), silu_half(fmaf(h1, bf_hi(sp), bf_hi(tp))));
    }
    auto store = [&](int box) {
      __syncwarp();
      out_store(c, A_X + (3 + box) * XSLOT + c.warp * 2048, box, c.b0 + 8, 1);
    };
    if constexpr ((j & 3) == 0 && j >= 4) store((j >> 2) - 1);
    stsm4(A_X + (3 + (j >> 2)) * XSLOT + c.warp * 2048 + (lane_stg ^ ((j & 3) << 5)), p[0], p[1], p[2], p[3]);
    if constexpr (j + TAILW < 14) lds128(pk + 4 * (j + TAILW), lane_par + (j + TAILW) * 64);
    if constexpr ((j & 3) == 3 || j == 13) FENCE_ASYNC_SMEM();
    if constexpr (j == 13) store(3);
  });
  asm volatile("cp.async.bulk.wait_group.read 0;" ::: "memory");
}

#undef zero
#undef seven

__global__ void weights_kernel(const __nv_bfloat16* w, char* scratch) {
  const int item = blockIdx.x * blockDim.x + threadIdx.x;
  const int ci = item / (CH / 2), d = (item - ci * (CH / 2)) * 2;
  const uint32_t* wp = (const uint32_t*)(w + ci * CH + d);
  const uint32_t g0 = wp[0], g1 = wp[CH * CH / 2], g2 = wp[CH * CH];
  const float sl = bf_lo(g0) + bf_lo(g2), sh = bf_hi(g0) + bf_hi(g2);
  const int h = d / 224, dd = h ? (d < 256 ? d - 32 : d - 256) : d;
  char* base = scratch + h * (NSCR * WBYTES) + (dd >> 5) * 2048 + ((((dd >> 3) & 3) ^ ((ci >> 1) & 3)) << 4) + (dd & 7) * 2;
  char* pT = base + (14 + (ci >> 4)) * WBYTES + (ci & 15) * 64;
  char* pE = base + (ci >> 5) * WBYTES + (ci & 31) * 64;
  *(uint32_t*)pT = pack_bf16(sl + bf_lo(g1), sh + bf_hi(g1));
  *(uint32_t*)(pT + 1024) = pack_bf16(sl - bf_lo(g1), sh - bf_hi(g1));
  *(uint32_t*)(pE + 42 * WBYTES) = pack_bf16(-2.f * bf_lo(g2), -2.f * bf_hi(g2));
  *(uint32_t*)pE = g0;
}

typedef CUresult (*EncodeFn)(CUtensorMap*, CUtensorMapDataType, cuuint32_t, void*, const cuuint64_t*, const cuuint64_t*,
                             const cuuint32_t*, const cuuint32_t*, CUtensorMapInterleave, CUtensorMapSwizzle,
                             CUtensorMapL2promotion, CUtensorMapFloatOOBfill);

}

extern "C" void kernel_launch(void* const* d_in, const int* in_sizes, int n_in, void* d_out, int out_size) {
  static EncodeFn encode = nullptr;
  static void* scratch = nullptr;
  static void* counters = nullptr;
  static int num_sms = 0;
  if (!encode) {
    void* fn = nullptr;
    cudaDriverEntryPointQueryResult st;
    cudaGetDriverEntryPoint("cuTensorMapEncodeTiled", &fn, cudaEnableDefault, &st);
    encode = (EncodeFn)fn;
    cudaGetSymbolAddress(&scratch, g_wscratch);
    cudaGetSymbolAddress(&counters, g_counters);
    int dev = 0;
    cudaGetDevice(&dev);
    cudaDeviceGetAttribute(&num_sms, cudaDevAttrMultiProcessorCount, dev);
    cudaFuncSetAttribute(conv_bn_silu_kernel, cudaFuncAttributeMaxDynamicSharedMemorySize, SMEM_BYTES);
  }
  Maps maps;
  const cuuint32_t ones[5] = {1, 1, 1, 1, 1};
  {
    const cuuint64_t dims[4] = {CH, NBATCH, 16, 2};
    const cuuint64_t strides[3] = {32 * CH * 2, 2 * CH * 2, CH * 2};
    const cuuint32_t boxx[4] = {64, 8, 16, 1};
    encode(&maps.x, CU_TENSOR_MAP_DATA_TYPE_BFLOAT16, 4, d_in[0], dims, strides, boxx, ones, CU_TENSOR_MAP_INTERLEAVE_NONE,
           CU_TENSOR_MAP_SWIZZLE_128B, CU_TENSOR_MAP_L2_PROMOTION_L2_128B, CU_TENSOR_MAP_FLOAT_OOB_FILL_NONE);
    const cuuint64_t dimo[5] = {224, NBATCH, 16, 2, 8};
    const cuuint64_t strideo[4] = {32 * CH * 2, 2 * CH * 2, CH * 2, 64};
    const cuuint32_t boxo[5] = {64, 8, 2, 1, 1};
    encode(&maps.o, CU_TENSOR_MAP_DATA_TYPE_BFLOAT16, 5, d_out, dimo, strideo, boxo, ones, CU_TENSOR_MAP_INTERLEAVE_NONE,
           CU_TENSOR_MAP_SWIZZLE_128B, CU_TENSOR_MAP_L2_PROMOTION_NONE, CU_TENSOR_MAP_FLOAT_OOB_FILL_NONE);
  }
  {
    const cuuint64_t dims[3] = {64, CH, 7};
    const cuuint64_t strides[2] = {CH * 2, 128};
    const cuuint32_t box[3] = {64, 32, 3};
    encode(&maps.w[0], CU_TENSOR_MAP_DATA_TYPE_BFLOAT16, 3, d_in[1], dims, strides, box, ones, CU_TENSOR_MAP_INTERLEAVE_NONE,
           CU_TENSOR_MAP_SWIZZLE_128B, CU_TENSOR_MAP_L2_PROMOTION_L2_128B, CU_TENSOR_MAP_FLOAT_OOB_FILL_NONE);
    const cuuint64_t dims2[3] = {224, CH, 2};
    const cuuint64_t strides2[2] = {CH * 2, 64};
    const cuuint32_t box2[3] = {64, 32, 1};
    encode(&maps.w[1], CU_TENSOR_MAP_DATA_TYPE_BFLOAT16, 3, d_in[1], dims2, strides2, box2, ones, CU_TENSOR_MAP_INTERLEAVE_NONE,
           CU_TENSOR_MAP_SWIZZLE_128B, CU_TENSOR_MAP_L2_PROMOTION_L2_128B, CU_TENSOR_MAP_FLOAT_OOB_FILL_NONE);
  }
  Params prm;
  prm.x = (const __nv_bfloat16*)d_in[0];
  prm.w = (const __nv_bfloat16*)d_in[1];
  prm.mean = (const __nv_bfloat16*)d_in[2];
  prm.var = (const __nv_bfloat16*)d_in[3];
  prm.g = (const __nv_bfloat16*)d_in[4];
  prm.b = (const __nv_bfloat16*)d_in[5];
  prm.scratch = (char*)scratch;
  prm.counters = (unsigned int*)counters;
  prm.need = NPUB;
  prm.zero_ = 0;
  prm.seven_ = 7;
  if (num_sms < NCTA) {
    weights_kernel<<<CH * CH / 2 / 256, 256>>>(prm.w, prm.scratch);
    prm.need = 0;
  }
  conv_bn_silu_kernel<<<NCTA, 256, SMEM_BYTES>>>(maps, prm);
}
```
